```python
import torch

def _softmax(x, axis=-1):
    return torch.softmax(x, dim=axis)
def _gelu(x):
    return torch.nn.functional.gelu(x, approximate="tanh")
def _silu(x):
    return torch.nn.functional.silu(x)
def _sigmoid(x):
    return torch.sigmoid(x)
def _layernorm(x, axis=-1, eps=1e-5):
    m = x.mean(dim=axis, keepdim=True)
    v = x.var(dim=axis, keepdim=True, unbiased=False)
    return (x - m) / torch.sqrt(v + eps)
def _scatter_add(tgt, idx, src, axis=0):
    return tgt.clone().index_add_(axis, idx, src)
def _segment_sum(src, seg, n):
    out = torch.zeros((n,) + src.shape[1:], dtype=src.dtype)
    return out.index_add_(0, seg, src)
def _pad(x, pw):
    flat = tuple(v for pair in reversed(pw) for v in pair)
    return torch.nn.functional.pad(x, flat)

kernel_name = 'sequential_preLN__compressed_kv_cla__glu_gated_glu__prompt'

def setup_inputs():

    _w = (lambda a: (lambda t: t.to(torch.bfloat16) if t.is_floating_point() else t)(torch.as_tensor(a)))
    def _A_setup():
        B, H, Sq, Sk, D, M = 1, 32, 2048, 2048, 128, 512
        Dc = 4 * D
        return {
            "x": _w((lambda *s: torch.randn(*s, dtype=torch.bfloat16) * 0.05)(B, Sq, M)),
            "c_kv": _w((lambda *s: torch.randn(*s, dtype=torch.bfloat16) * 0.4)(B, Sk, Dc)),
            "w_q": _w((lambda *s: torch.randn(*s, dtype=torch.bfloat16) * 3.2)(M, H, D) * (M ** -0.5)),
            "w_uk": _w((lambda *s: torch.randn(*s, dtype=torch.bfloat16) * 3.2)(Dc, H, D) * (Dc ** -0.5)),
            "w_uv": _w((lambda *s: torch.randn(*s, dtype=torch.bfloat16) * 0.4)(Dc, H, D) * (Dc ** -0.5)),
            "w_o": _w((lambda *s: torch.randn(*s, dtype=torch.bfloat16) * 0.4)(H, D, M) * ((H * D) ** -0.5)),
        }
    _A_in = _A_setup()

    def _B_setup():
        B, S, D, F = 1, 2048, 512, 1792
        return {
            "x": _w((lambda *s: torch.randn(*s, dtype=torch.bfloat16) * 0.05)(B, S, D)),
            "w_gate": _w((lambda *s: torch.randn(*s, dtype=torch.bfloat16) * 0.05)(D, F)),
            "w_up": _w((lambda *s: torch.randn(*s, dtype=torch.bfloat16) * 0.05)(D, F)),
            "w_down": _w((lambda *s: torch.randn(*s, dtype=torch.bfloat16) * 0.05)(F, D)),
        }
    _B_in = _B_setup()

    return {
        "A_x": _A_in["x"],
        "A_c_kv": _A_in["c_kv"],
        "A_w_q": _A_in["w_q"],
        "A_w_uk": _A_in["w_uk"],
        "A_w_uv": _A_in["w_uv"],
        "A_w_o": _A_in["w_o"],
        "B_x": _B_in["x"],
        "B_w_gate": _B_in["w_gate"],
        "B_w_up": _B_in["w_up"],
        "B_w_down": _B_in["w_down"],
    }

def reference(A_x, A_c_kv, A_w_q, A_w_uk, A_w_uv, A_w_o, B_x, B_w_gate, B_w_up, B_w_down):
    def _A_ref(x, c_kv, w_q, w_uk, w_uv, w_o):
        B, Sq, M = x.shape[0], x.shape[1], x.shape[2]
        Sk = c_kv.shape[1]
        H, D = w_q.shape[1], w_q.shape[2]
        q = torch.einsum("bqm,mhd->bhqd", x, w_q)
        k = torch.einsum("bkc,chd->bhkd", c_kv, w_uk)
        v = torch.einsum("bkc,chd->bhkd", c_kv, w_uv)
        scores = torch.einsum("bhqd,bhkd->bhqk", q, k) * (D ** -0.5)
        off = Sk - Sq
        qi = torch.arange(Sq)[:, None]
        kj = torch.arange(Sk)[None, :]
        cmask = kj <= (qi + off)
        scores = torch.where(cmask[None, None], scores, -1e9)
        p = _softmax(scores, axis=-1)
        ctx = torch.einsum("bhqk,bhkd->bhqd", p, v)
        return torch.einsum("bhqd,hdm->bqm", ctx, w_o)

    def _B_ref(x, w_gate, w_up, w_down):
        g = torch.einsum("bsd,df->bsf", x, w_gate)
        u = torch.einsum("bsd,df->bsf", x, w_up)
        h = _sigmoid(g) * u
        return torch.einsum("bsf,fd->bsd", h, w_down)

    x = A_x
    h = x + _A_ref(_layernorm(x, axis=-1), A_c_kv, A_w_q, A_w_uk, A_w_uv, A_w_o)
    h2 = h + _B_ref(_layernorm(h, axis=-1), B_w_gate, B_w_up, B_w_down)
    return h2
```

```cpp
#include <cuda_runtime.h>
#include <cuda_bf16.h>
#include <cuda.h>
#include <stdint.h>
#include <type_traits>

typedef __nv_bfloat16 bf16;

constexpr int S_LEN = 2048;
constexpr int DM    = 512;
constexpr int NH    = 32;
constexpr int HD    = 128;
constexpr int HDM   = NH * HD;
constexpr int FF    = 1792;
constexpr int NSPLIT = 8;
constexpr float LN_EPS = 1e-5f;

__device__ __align__(1024) bf16 g_xn[S_LEN * DM];
__device__ __align__(1024) bf16 g_qkv[3 * NH * S_LEN * HD];
__device__ unsigned g_ln_cnt[16];
__device__ __align__(1024) bf16 g_ctx[S_LEN * HDM];
__device__ __align__(1024) float g_cs[2 * FF];
__device__ __align__(1024) unsigned g_tail_cnt[16 * 32];

__device__ __forceinline__ uint32_t smem_u32(const void* p) { return (uint32_t)__cvta_generic_to_shared(p); }
__device__ __forceinline__ void mbar_init(uint32_t bar, uint32_t count) {
  asm volatile("mbarrier.init.shared::cta.b64 [%0], %1;" :: "r"(bar), "r"(count));
}
__device__ __forceinline__ void mbar_expect_tx(uint32_t bar, uint32_t bytes) {
  asm volatile("mbarrier.arrive.expect_tx.shared::cta.b64 _, [%0], %1;" :: "r"(bar), "r"(bytes) : "memory");
}
__device__ __forceinline__ void mbar_arrive(uint32_t bar) {
  asm volatile("mbarrier.arrive.shared::cta.b64 _, [%0];" :: "r"(bar) : "memory");
}
__device__ __forceinline__ void mbar_arrive_cluster(uint32_t bar, uint32_t cta) {
  asm volatile("{\n.reg .b32 ra;\nmapa.shared::cluster.u32 ra, %0, %1;\nmbarrier.arrive.shared::cluster.b64 _, [ra];\n}"
               :: "r"(bar), "r"(cta) : "memory");
}
__device__ __forceinline__ bool mbar_try_wait(uint32_t bar, uint32_t parity) {
  uint32_t ok;
  asm volatile("{\n.reg .pred p;\nmbarrier.try_wait.parity.shared::cta.b64 p, [%1], %2;\nselp.u32 %0, 1, 0, p;\n}"
               : "=r"(ok) : "r"(bar), "r"(parity) : "memory");
  return ok;
}
__device__ __forceinline__ void mbar_wait(uint32_t bar, uint32_t parity) {
  if (mbar_try_wait(bar, parity)) return;
  #pragma unroll 1
  for (int i = 0; i < (1 << 20); i++) { if (mbar_try_wait(bar, parity)) return; }
  __trap();
}
__device__ __forceinline__ void tma_load_2d(uint32_t dst, const CUtensorMap* map, int c0, int c1, uint32_t bar) {
  asm volatile("cp.async.bulk.tensor.2d.shared::cluster.global.mbarrier::complete_tx::bytes [%0], [%1, {%3, %4}], [%2];"
               :: "r"(dst), "l"(map), "r"(bar), "r"(c0), "r"(c1) : "memory");
}
__device__ __forceinline__ void tma_load_2d_mc(uint32_t dst, const CUtensorMap* map, int c0, int c1, uint32_t bar) {
  asm volatile("cp.async.bulk.tensor.2d.shared::cluster.global.mbarrier::complete_tx::bytes.multicast::cluster [%0], [%1, {%3, %4}], [%2], %5;"
               :: "r"(dst), "l"(map), "r"(bar), "r"(c0), "r"(c1), "h"((uint16_t)3) : "memory");
}
__device__ __forceinline__ void tma_store_2d(const CUtensorMap* map, uint32_t src, int c0, int c1) {
  asm volatile("cp.async.bulk.tensor.2d.global.shared::cta.bulk_group [%0, {%2, %3}], [%1];"
               :: "l"(map), "r"(src), "r"(c0), "r"(c1) : "memory");
}
__device__ __forceinline__ void tma_prefetch_2d(const CUtensorMap* map, int c0, int c1) {
  asm volatile("cp.async.bulk.prefetch.tensor.2d.L2.global.tile [%0, {%1, %2}];" :: "l"(map), "r"(c0), "r"(c1) : "memory");
}
__device__ __forceinline__ void l2_prefetch(const void* p, uint32_t bytes) {
  asm volatile("cp.async.bulk.prefetch.L2.global [%0], %1;" :: "l"(p), "r"(bytes) : "memory");
}
__device__ __forceinline__ void prefetch_map(const CUtensorMap* map) {
  asm volatile("prefetch.tensormap [%0];" :: "l"(map) : "memory");
}
__device__ __forceinline__ void bulk_commit() { asm volatile("cp.async.bulk.commit_group;" ::: "memory"); }
__device__ __forceinline__ void bulk_wait_read0() { asm volatile("cp.async.bulk.wait_group.read 0;" ::: "memory"); }
__device__ __forceinline__ void bulk_wait0() { asm volatile("cp.async.bulk.wait_group 0;" ::: "memory"); }
__device__ __forceinline__ void fence_proxy_async() { asm volatile("fence.proxy.async.shared::cta;" ::: "memory"); }
__device__ __forceinline__ void wgmma_fence() { asm volatile("wgmma.fence.sync.aligned;" ::: "memory"); }
__device__ __forceinline__ void wgmma_commit() { asm volatile("wgmma.commit_group.sync.aligned;" ::: "memory"); }
template <int N> __device__ __forceinline__ void wgmma_wait() { asm volatile("wgmma.wait_group.sync.aligned %0;" :: "n"(N) : "memory"); }
__device__ __forceinline__ void cluster_arrive() { asm volatile("barrier.cluster.arrive.release.aligned;" ::: "memory"); }
__device__ __forceinline__ void cluster_arrive_relaxed() { asm volatile("barrier.cluster.arrive.relaxed.aligned;" ::: "memory"); }
__device__ __forceinline__ void cluster_wait() { asm volatile("barrier.cluster.wait.acquire.aligned;" ::: "memory"); }
__device__ __forceinline__ uint32_t cluster_ctarank() { uint32_t r; asm volatile("mov.u32 %0, %%cluster_ctarank;" : "=r"(r)); return r; }
__device__ __forceinline__ void bar_sync(int id, int n) { asm volatile("bar.sync %0, %1;" :: "r"(id), "r"(n) : "memory"); }
__device__ __forceinline__ void bar_arrive(int id, int n) { asm volatile("bar.arrive %0, %1;" :: "r"(id), "r"(n) : "memory"); }
__device__ __forceinline__ void pdl_wait() { asm volatile("griddepcontrol.wait;" ::: "memory"); }
__device__ __forceinline__ void pdl_launch() { asm volatile("griddepcontrol.launch_dependents;" ::: "memory"); }
template <int R> __device__ __forceinline__ void reg_alloc() { asm volatile("setmaxnreg.inc.sync.aligned.u32 %0;" :: "n"(R)); }
template <int R> __device__ __forceinline__ void reg_dealloc() { asm volatile("setmaxnreg.dec.sync.aligned.u32 %0;" :: "n"(R)); }
__device__ __forceinline__ uint64_t make_desc(uint32_t addr, uint32_t lbo_bytes, uint32_t sbo_bytes) {
  uint64_t d = 0;
  d |= (uint64_t)((addr & 0x3FFFF) >> 4);
  d |= (uint64_t)((lbo_bytes >> 4) & 0x3FFF) << 16;
  d |= (uint64_t)((sbo_bytes >> 4) & 0x3FFF) << 32;
  d |= (uint64_t)1 << 62;
  return d;
}
__device__ __forceinline__ uint32_t pack_bf16(float lo, float hi) {
  uint32_t r;
  asm("cvt.rn.bf16x2.f32 %0, %1, %2;" : "=r"(r) : "f"(hi), "f"(lo));
  return r;
}
__device__ __forceinline__ void stmatrix_x4(uint32_t addr, uint32_t r0, uint32_t r1, uint32_t r2, uint32_t r3) {
  asm volatile("stmatrix.sync.aligned.m8n8.x4.shared.b16 [%0], {%1, %2, %3, %4};"
               :: "r"(addr), "r"(r0), "r"(r1), "r"(r2), "r"(r3) : "memory");
}
__device__ __forceinline__ void ldmatrix_x4(uint32_t addr, uint32_t& r0, uint32_t& r1, uint32_t& r2, uint32_t& r3) {
  asm volatile("ldmatrix.sync.aligned.m8n8.x4.shared.b16 {%0, %1, %2, %3}, [%4];"
               : "=r"(r0), "=r"(r1), "=r"(r2), "=r"(r3) : "r"(addr) : "memory");
}
__device__ __forceinline__ void fence_proxy_async_all() { asm volatile("fence.proxy.async;" ::: "memory"); }
__device__ __forceinline__ unsigned ld_acquire(const unsigned* p) {
  unsigned v; asm volatile("ld.acquire.gpu.global.u32 %0, [%1];" : "=r"(v) : "l"(p) : "memory"); return v;
}
__device__ __forceinline__ float ex2(float x) { float y; asm("ex2.approx.ftz.f32 %0, %1;" : "=f"(y) : "f"(x)); return y; }
template <int N> __device__ __forceinline__ void fence_regs(float (&d)[N]) {
  #pragma unroll
  for (int i = 0; i < N; i++) asm volatile("" : "+f"(d[i]) :: "memory");
}
template <int N> __device__ __forceinline__ void fence_regs(uint32_t (&d)[N]) {
  #pragma unroll
  for (int i = 0; i < N; i++) asm volatile("" : "+r"(d[i]) :: "memory");
}


__device__ __forceinline__ void wgmma_ss_n128_tb(float (&d)[64], uint64_t descA, uint64_t descB, int scaleD) {
  asm volatile("{\n.reg .pred p;\n"
    "setp.ne.b32 p, %66, 0;\n"
    "wgmma.mma_async.sync.aligned.m64n128k16.f32.bf16.bf16 "
    "{%0, %1, %2, %3, %4, %5, %6, %7, %8, %9, %10, %11, %12, %13, %14, %15, %16, %17, %18, %19, %20, %21, %22, %23, %24, %25, %26, %27, %28, %29, %30, %31, %32, %33, %34, %35, %36, %37, %38, %39, %40, %41, %42, %43, %44, %45, %46, %47, %48, %49, %50, %51, %52, %53, %54, %55, %56, %57, %58, %59, %60, %61, %62, %63}, "
    "%64, %65, p, 1, 1, 0, 1;\n}\n"
    : "+f"(d[0]), "+f"(d[1]), "+f"(d[2]), "+f"(d[3]), "+f"(d[4]), "+f"(d[5]), "+f"(d[6]), "+f"(d[7]),
      "+f"(d[8]), "+f"(d[9]), "+f"(d[10]), "+f"(d[11]), "+f"(d[12]), "+f"(d[13]), "+f"(d[14]), "+f"(d[15]),
      "+f"(d[16]), "+f"(d[17]), "+f"(d[18]), "+f"(d[19]), "+f"(d[20]), "+f"(d[21]), "+f"(d[22]), "+f"(d[23]),
      "+f"(d[24]), "+f"(d[25]), "+f"(d[26]), "+f"(d[27]), "+f"(d[28]), "+f"(d[29]), "+f"(d[30]), "+f"(d[31]),
      "+f"(d[32]), "+f"(d[33]), "+f"(d[34]), "+f"(d[35]), "+f"(d[36]), "+f"(d[37]), "+f"(d[38]), "+f"(d[39]),
      "+f"(d[40]), "+f"(d[41]), "+f"(d[42]), "+f"(d[43]), "+f"(d[44]), "+f"(d[45]), "+f"(d[46]), "+f"(d[47]),
      "+f"(d[48]), "+f"(d[49]), "+f"(d[50]), "+f"(d[51]), "+f"(d[52]), "+f"(d[53]), "+f"(d[54]), "+f"(d[55]),
      "+f"(d[56]), "+f"(d[57]), "+f"(d[58]), "+f"(d[59]), "+f"(d[60]), "+f"(d[61]), "+f"(d[62]), "+f"(d[63])
    : "l"(descA), "l"(descB), "r"(scaleD));
}
__device__ __forceinline__ void wgmma_rs_n128(float (&d)[64], uint32_t a0, uint32_t a1, uint32_t a2, uint32_t a3, uint64_t descB, int scaleD) {
  asm volatile("{\n.reg .pred p;\n"
    "setp.ne.b32 p, %69, 0;\n"
    "wgmma.mma_async.sync.aligned.m64n128k16.f32.bf16.bf16 "
    "{%0, %1, %2, %3, %4, %5, %6, %7, %8, %9, %10, %11, %12, %13, %14, %15, %16, %17, %18, %19, %20, %21, %22, %23, %24, %25, %26, %27, %28, %29, %30, %31, %32, %33, %34, %35, %36, %37, %38, %39, %40, %41, %42, %43, %44, %45, %46, %47, %48, %49, %50, %51, %52, %53, %54, %55, %56, %57, %58, %59, %60, %61, %62, %63}, "
    "{%64, %65, %66, %67}, %68, p, 1, 1, 0;\n}\n"
    : "+f"(d[0]), "+f"(d[1]), "+f"(d[2]), "+f"(d[3]), "+f"(d[4]), "+f"(d[5]), "+f"(d[6]), "+f"(d[7]),
      "+f"(d[8]), "+f"(d[9]), "+f"(d[10]), "+f"(d[11]), "+f"(d[12]), "+f"(d[13]), "+f"(d[14]), "+f"(d[15]),
      "+f"(d[16]), "+f"(d[17]), "+f"(d[18]), "+f"(d[19]), "+f"(d[20]), "+f"(d[21]), "+f"(d[22]), "+f"(d[23]),
      "+f"(d[24]), "+f"(d[25]), "+f"(d[26]), "+f"(d[27]), "+f"(d[28]), "+f"(d[29]), "+f"(d[30]), "+f"(d[31]),
      "+f"(d[32]), "+f"(d[33]), "+f"(d[34]), "+f"(d[35]), "+f"(d[36]), "+f"(d[37]), "+f"(d[38]), "+f"(d[39]),
      "+f"(d[40]), "+f"(d[41]), "+f"(d[42]), "+f"(d[43]), "+f"(d[44]), "+f"(d[45]), "+f"(d[46]), "+f"(d[47]),
      "+f"(d[48]), "+f"(d[49]), "+f"(d[50]), "+f"(d[51]), "+f"(d[52]), "+f"(d[53]), "+f"(d[54]), "+f"(d[55]),
      "+f"(d[56]), "+f"(d[57]), "+f"(d[58]), "+f"(d[59]), "+f"(d[60]), "+f"(d[61]), "+f"(d[62]), "+f"(d[63])
    : "r"(a0), "r"(a1), "r"(a2), "r"(a3), "l"(descB), "r"(scaleD));
}
__device__ __forceinline__ void wgmma_rs_n128_tb(float (&d)[64], uint32_t a0, uint32_t a1, uint32_t a2, uint32_t a3, uint64_t descB, int scaleD) {
  asm volatile("{\n.reg .pred p;\n"
    "setp.ne.b32 p, %69, 0;\n"
    "wgmma.mma_async.sync.aligned.m64n128k16.f32.bf16.bf16 "
    "{%0, %1, %2, %3, %4, %5, %6, %7, %8, %9, %10, %11, %12, %13, %14, %15, %16, %17, %18, %19, %20, %21, %22, %23, %24, %25, %26, %27, %28, %29, %30, %31, %32, %33, %34, %35, %36, %37, %38, %39, %40, %41, %42, %43, %44, %45, %46, %47, %48, %49, %50, %51, %52, %53, %54, %55, %56, %57, %58, %59, %60, %61, %62, %63}, "
    "{%64, %65, %66, %67}, %68, p, 1, 1, 1;\n}\n"
    : "+f"(d[0]), "+f"(d[1]), "+f"(d[2]), "+f"(d[3]), "+f"(d[4]), "+f"(d[5]), "+f"(d[6]), "+f"(d[7]),
      "+f"(d[8]), "+f"(d[9]), "+f"(d[10]), "+f"(d[11]), "+f"(d[12]), "+f"(d[13]), "+f"(d[14]), "+f"(d[15]),
      "+f"(d[16]), "+f"(d[17]), "+f"(d[18]), "+f"(d[19]), "+f"(d[20]), "+f"(d[21]), "+f"(d[22]), "+f"(d[23]),
      "+f"(d[24]), "+f"(d[25]), "+f"(d[26]), "+f"(d[27]), "+f"(d[28]), "+f"(d[29]), "+f"(d[30]), "+f"(d[31]),
      "+f"(d[32]), "+f"(d[33]), "+f"(d[34]), "+f"(d[35]), "+f"(d[36]), "+f"(d[37]), "+f"(d[38]), "+f"(d[39]),
      "+f"(d[40]), "+f"(d[41]), "+f"(d[42]), "+f"(d[43]), "+f"(d[44]), "+f"(d[45]), "+f"(d[46]), "+f"(d[47]),
      "+f"(d[48]), "+f"(d[49]), "+f"(d[50]), "+f"(d[51]), "+f"(d[52]), "+f"(d[53]), "+f"(d[54]), "+f"(d[55]),
      "+f"(d[56]), "+f"(d[57]), "+f"(d[58]), "+f"(d[59]), "+f"(d[60]), "+f"(d[61]), "+f"(d[62]), "+f"(d[63])
    : "r"(a0), "r"(a1), "r"(a2), "r"(a3), "l"(descB), "r"(scaleD));
}
__device__ __forceinline__ void wgmma_ss_n32_tb(float (&d)[16], uint64_t descA, uint64_t descB, int scaleD) {
  asm volatile("{\n.reg .pred p;\n"
    "setp.ne.b32 p, %18, 0;\n"
    "wgmma.mma_async.sync.aligned.m64n32k16.f32.bf16.bf16 "
    "{%0, %1, %2, %3, %4, %5, %6, %7, %8, %9, %10, %11, %12, %13, %14, %15}, "
    "%16, %17, p, 1, 1, 0, 1;\n}\n"
    : "+f"(d[0]), "+f"(d[1]), "+f"(d[2]), "+f"(d[3]), "+f"(d[4]), "+f"(d[5]), "+f"(d[6]), "+f"(d[7]),
      "+f"(d[8]), "+f"(d[9]), "+f"(d[10]), "+f"(d[11]), "+f"(d[12]), "+f"(d[13]), "+f"(d[14]), "+f"(d[15])
    : "l"(descA), "l"(descB), "r"(scaleD));
}
__device__ __forceinline__ void wgmma_rs_n64(float (&d)[32], uint32_t a0, uint32_t a1, uint32_t a2, uint32_t a3, uint64_t descB, int scaleD) {
  asm volatile("{\n.reg .pred p;\n"
    "setp.ne.b32 p, %37, 0;\n"
    "wgmma.mma_async.sync.aligned.m64n64k16.f32.bf16.bf16 "
    "{%0, %1, %2, %3, %4, %5, %6, %7, %8, %9, %10, %11, %12, %13, %14, %15, %16, %17, %18, %19, %20, %21, %22, %23, %24, %25, %26, %27, %28, %29, %30, %31}, "
    "{%32, %33, %34, %35}, %36, p, 1, 1, 0;\n}\n"
    : "+f"(d[0]), "+f"(d[1]), "+f"(d[2]), "+f"(d[3]), "+f"(d[4]), "+f"(d[5]), "+f"(d[6]), "+f"(d[7]),
      "+f"(d[8]), "+f"(d[9]), "+f"(d[10]), "+f"(d[11]), "+f"(d[12]), "+f"(d[13]), "+f"(d[14]), "+f"(d[15]),
      "+f"(d[16]), "+f"(d[17]), "+f"(d[18]), "+f"(d[19]), "+f"(d[20]), "+f"(d[21]), "+f"(d[22]), "+f"(d[23]),
      "+f"(d[24]), "+f"(d[25]), "+f"(d[26]), "+f"(d[27]), "+f"(d[28]), "+f"(d[29]), "+f"(d[30]), "+f"(d[31])
    : "r"(a0), "r"(a1), "r"(a2), "r"(a3), "l"(descB), "r"(scaleD));
}
template <int OFF>
__device__ __forceinline__ void wgmma_rs_n32_tb(float (&d)[64], uint32_t a0, uint32_t a1, uint32_t a2, uint32_t a3, uint64_t descB, int scaleD) {
  asm volatile("{\n.reg .pred p;\n"
    "setp.ne.b32 p, %21, 0;\n"
    "wgmma.mma_async.sync.aligned.m64n32k16.f32.bf16.bf16 "
    "{%0, %1, %2, %3, %4, %5, %6, %7, %8, %9, %10, %11, %12, %13, %14, %15}, "
    "{%16, %17, %18, %19}, %20, p, 1, 1, 1;\n}\n"
    : "+f"(d[OFF + 0]), "+f"(d[OFF + 1]), "+f"(d[OFF + 2]), "+f"(d[OFF + 3]), "+f"(d[OFF + 4]), "+f"(d[OFF + 5]), "+f"(d[OFF + 6]), "+f"(d[OFF + 7]), "+f"(d[OFF + 8]), "+f"(d[OFF + 9]), "+f"(d[OFF + 10]), "+f"(d[OFF + 11]), "+f"(d[OFF + 12]), "+f"(d[OFF + 13]), "+f"(d[OFF + 14]), "+f"(d[OFF + 15])
    : "r"(a0), "r"(a1), "r"(a2), "r"(a3), "l"(descB), "r"(scaleD));
}

__device__ __forceinline__ void release_slot(uint32_t empty_bar, int tid_wg) {
  if ((tid_wg & 95) == 0) mbar_arrive_cluster(empty_bar, tid_wg >> 5);
}

struct Ring { uint32_t slot; uint32_t phase; };

__device__ __forceinline__ float warp_sum(float v) {
  #pragma unroll
  for (int o = 16; o > 0; o >>= 1) v += __shfl_xor_sync(0xffffffffu, v, o);
  return v;
}
__device__ __forceinline__ void unpack8(const uint4& u, float (&f)[8]) {
  const uint32_t w[4] = {u.x, u.y, u.z, u.w};
  #pragma unroll
  for (int i = 0; i < 4; i++) { f[2 * i] = __uint_as_float(w[i] << 16); f[2 * i + 1] = __uint_as_float(w[i] & 0xffff0000u); }
}
__device__ __forceinline__ uint4 pack8(const float (&f)[8]) {
  uint4 u; u.x = pack_bf16(f[0], f[1]); u.y = pack_bf16(f[2], f[3]); u.z = pack_bf16(f[4], f[5]); u.w = pack_bf16(f[6], f[7]);
  return u;
}
__device__ __forceinline__ void ln_row(float (&a)[8], float (&b)[8]) {
  float s = 0.f;
  #pragma unroll
  for (int i = 0; i < 8; i++) s += a[i] + b[i];
  const float mean = warp_sum(s) * (1.0f / DM);
  float v = 0.f;
  #pragma unroll
  for (int i = 0; i < 8; i++) { a[i] -= mean; b[i] -= mean; v += a[i] * a[i] + b[i] * b[i]; }
  const float rstd = rsqrtf(warp_sum(v) * (1.0f / DM) + LN_EPS);
  #pragma unroll
  for (int i = 0; i < 8; i++) { a[i] *= rstd; b[i] *= rstd; }
}

constexpr int R_NS = 12;
constexpr int R_ST = R_NS * 16384;
constexpr int R_BAR = R_ST + 32768;
constexpr int R_SMEM = R_BAR + 256;
constexpr int R_FULL = R_BAR, R_EMPTY = R_BAR + 128;
#define HANDOFF 7
__device__ __forceinline__ void rnext(Ring& r) { if (++r.slot == R_NS) { r.slot = 0; r.phase ^= 1; } }

__device__ __forceinline__ void fetch_a(uint32_t (&a)[128], int kc, uint32_t src, uint32_t fx, uint32_t fhi) {
  #pragma unroll
  for (int k = 0; k < 4; k++)
    ldmatrix_x4(src + (((k * 2 + fhi) ^ fx) << 4), a[16 * kc + 4 * k], a[16 * kc + 4 * k + 1], a[16 * kc + 4 * k + 2], a[16 * kc + 4 * k + 3]);
}
struct RsCtx { uint32_t sb, arow, fx, fhi; int wg, tid_wg, kid; };

#define WAIT0 5
__device__ __forceinline__ bool mbar_test(uint32_t bar, uint32_t parity) {
  uint32_t ok;
  asm volatile("{\n.reg .pred p;\nmbarrier.test_wait.parity.shared::cta.b64 p, [%1], %2;\nselp.u32 %0, 1, 0, p;\n}"
               : "=r"(ok) : "r"(bar), "r"(parity) : "memory");
  return ok;
}
template <bool FIRST>
__device__ __forceinline__ void rs_tile(float (&acc)[64], uint32_t (&a)[128], const RsCtx& c, Ring& r, bool tok_wait, bool tok_pass) {
  uint32_t b1 = 0, b2 = 0, a1 = 0, a2 = 0, curA = 0;
  bool ok = false;
  #pragma unroll
  for (int ks = 0; ks < 8; ks++) {
    if (FIRST) {
      mbar_wait(c.sb + R_FULL + r.slot * 8, r.phase);
      fetch_a(a, ks, c.sb + r.slot * 16384 + c.arow, c.fx, c.fhi);
      curA = r.slot; rnext(r);
    }
    if (!ok) mbar_wait(c.sb + R_FULL + r.slot * 8, r.phase);
    if (ks == (FIRST ? WAIT0 : 0) && tok_wait) bar_sync(1 + c.wg, 256);
    const uint64_t dB = make_desc(c.sb + r.slot * 16384, 8192, 1024);
    const uint32_t b0 = r.slot;
    rnext(r);
    wgmma_fence();
    #pragma unroll
    for (int k = 0; k < 4; k++) {
      wgmma_rs_n128_tb(acc, a[16 * ks + 4 * k], a[16 * ks + 4 * k + 1], a[16 * ks + 4 * k + 2], a[16 * ks + 4 * k + 3], dB + k * 128, (ks | k) != 0);
      if (k == 0 && ks >= 2) {
        wgmma_wait<1>();
        release_slot(c.sb + R_EMPTY + b2 * 8, c.tid_wg);
        if (FIRST) release_slot(c.sb + R_EMPTY + a2 * 8, c.tid_wg);
      }
      if (k == 1 && !FIRST && ks < 7) ok = mbar_test(c.sb + R_FULL + r.slot * 8, r.phase);
    }
    wgmma_commit();
    if (ks == (FIRST ? 7 : HANDOFF) && tok_pass) bar_arrive(2 - c.wg, 256);
    b2 = b1; b1 = b0; a2 = a1; a1 = curA;
  }
  wgmma_wait<1>();
  release_slot(c.sb + R_EMPTY + b2 * 8, c.tid_wg);
  if (FIRST) release_slot(c.sb + R_EMPTY + a2 * 8, c.tid_wg);
  wgmma_wait<0>();
  fence_regs(acc);
  release_slot(c.sb + R_EMPTY + b1 * 8, c.tid_wg);
  if (FIRST) release_slot(c.sb + R_EMPTY + a1 * 8, c.tid_wg);
}
__device__ __forceinline__ void rs_swap_a(uint32_t (&a)[128], const RsCtx& c, Ring& r) {
  #pragma unroll
  for (int kc = 0; kc < 8; kc++) {
    mbar_wait(c.sb + R_FULL + r.slot * 8, r.phase);
    fetch_a(a, kc, c.sb + r.slot * 16384 + c.arow, c.fx, c.fhi);
    bar_sync(3 + c.wg, 128);
    release_slot(c.sb + R_EMPTY + r.slot * 8, c.tid_wg);
    rnext(r);
  }
}
__device__ __forceinline__ void store_tile(const float (&acc)[64], uint32_t wbase, int lane, const CUtensorMap* map, int c0, int c1) {
  if (lane == 0) bulk_wait_read0();
  __syncwarp();
  const int row = (lane & 7) + ((lane >> 3) & 1) * 8;
  const uint32_t rbase = wbase + row * 128;
  #pragma unroll
  for (int q = 0; q < 8; q++) {
    const int j = 2 * q;
    const int chunk = 2 * (q & 3) + (lane >> 4);
    stmatrix_x4(rbase + (q >> 2) * 2048 + ((chunk ^ (row & 7)) << 4),
                pack_bf16(acc[4 * j + 0], acc[4 * j + 1]), pack_bf16(acc[4 * j + 2], acc[4 * j + 3]),
                pack_bf16(acc[4 * j + 4], acc[4 * j + 5]), pack_bf16(acc[4 * j + 6], acc[4 * j + 7]));
  }
  fence_proxy_async();
  __syncwarp();
  if (lane == 0) { tma_store_2d(map, wbase, c0, c1); tma_store_2d(map, wbase + 2048, c0 + 64, c1); bulk_commit(); }
}

#define KVS 0x566789BCu
constexpr uint32_t KV_SPLIT = KVS;
template <int MODE>
__global__ void __launch_bounds__(384, 1)
gemm_kernel(const __grid_constant__ CUtensorMap mapA, const __grid_constant__ CUtensorMap mapA2,
            const __grid_constant__ CUtensorMap mapB0, const __grid_constant__ CUtensorMap mapB1,
            const __grid_constant__ CUtensorMap mapB2, const __grid_constant__ CUtensorMap mapO,
            const bf16* __restrict__ x, const bf16* __restrict__ pa, const bf16* __restrict__ pb0, const bf16* __restrict__ pb1,
            const bf16* __restrict__ wgate, const bf16* __restrict__ wup, bf16* __restrict__ out) {
  extern __shared__ __align__(1024) uint8_t smem[];
  const uint32_t sb = smem_u32(smem);
  const int tid = threadIdx.x;
  const int wgi = __shfl_sync(0xffffffffu, tid >> 7, 0);
  const uint32_t rank = cluster_ctarank();
  const int cl = blockIdx.x >> 1;
  constexpr int NT = MODE == 0 ? 12 : 4;
  const int mtile = (cl & 7) * 2 + rank;
  const int grp = cl >> 3;
  int nkv = NT, kv0 = 0;
  if (MODE == 0) {
    nkv = (KV_SPLIT >> (4 * grp)) & 15;
    for (int g = 0; g < grp; g++) kv0 += (KV_SPLIT >> (4 * g)) & 15;
  }
  const int q0 = 2 * NH + 12 * grp - kv0 - nkv;
  const int ak0 = MODE == 0 ? 0 : grp * 512;
  auto slot_of = [&](int t) { return t < nkv ? kv0 + t : q0 + t; };
  auto bmap = [&](int t) { if (MODE == 1) return &mapB0; const int h = slot_of(t); return h < NH ? &mapB0 : (h < 2 * NH ? &mapB1 : &mapB2); };
  auto bcol = [&](int t) { return (MODE == 1 ? t : (slot_of(t) & (NH - 1))) * 128 + (int)rank * 64; };
  auto put_b = [&](int slot, int t, int ks) {
    mbar_expect_tx(sb + R_FULL + slot * 8, 16384);
    tma_load_2d_mc(sb + slot * 16384 + rank * 8192, bmap(t), bcol(t), ak0 + ks * 64, sb + R_FULL + slot * 8);
  };
  auto put_a = [&](int slot, const CUtensorMap* m, int kc) {
    mbar_expect_tx(sb + R_FULL + slot * 8, 16384);
    tma_load_2d(sb + slot * 16384, m, ak0 + kc * 64, mtile * 128, sb + R_FULL + slot * 8);
  };
  if (MODE == 0) {
    const bf16* q = tid >= 128 ? pa + (size_t)(mtile * 128 + (tid & 127)) * DM + (tid >> 8) * 64
                               : (kv0 < NH ? pb0 : pb1) + (size_t)tid * HDM + bcol(0);
    asm volatile("prefetch.global.L2 [%0];" :: "l"(q));
  }
  if (MODE == 0 && tid == 32) l2_prefetch(x + (size_t)(mtile * 128 + grp * 16) * DM, 16 * DM * 2);
  if (MODE == 0 && blockIdx.x == 0 && tid >= 128) { g_tail_cnt[tid - 128] = 0; g_tail_cnt[tid + 128] = 0; }
  if (tid == 0) {
    prefetch_map(&mapA); prefetch_map(bmap(0));
    for (int i = 0; i < R_NS; i++) { mbar_init(sb + R_FULL + i * 8, 1); mbar_init(sb + R_EMPTY + i * 8, 4); }
    asm volatile("fence.mbarrier_init.release.cluster;" ::: "memory");
    fence_proxy_async();
    if (MODE == 0) put_a(0, &mapA, 0);
  }
  __syncthreads();
  cluster_arrive_relaxed(); cluster_wait();
  if (tid == 0)
    for (int ks = 0; ks < R_NS / 2; ks++) {
      if (MODE == 0 && ks > 0) put_a(2 * ks, &mapA, ks);
      put_b(2 * ks + 1, 0, ks);
    }
  pdl_launch();

  if (wgi == 0) {
    reg_dealloc<40>();
    if (tid == 0) {
      prefetch_map(&mapO);
      Ring r{0, 0};
      auto load_b = [&](int t, int ks) { mbar_wait(sb + R_EMPTY + r.slot * 8, r.phase); put_b(r.slot, t, ks); rnext(r); };
      auto load_a = [&](const CUtensorMap* m, int kc) { mbar_wait(sb + R_EMPTY + r.slot * 8, r.phase); put_a(r.slot, m, kc); rnext(r); };
      auto pf_b = [&](int t) {
        if (t < NT) tma_prefetch_2d(bmap(t), bcol(t), ak0 + (cl & 7) * 64);
      };
      if (MODE == 0) { pf_b(1); pf_b(2); }
      else {
        pdl_wait();
        for (int ks = 0; ks < R_NS / 2; ks++) put_a(2 * ks, &mapA, ks);
      }
      for (int ks = R_NS / 2; ks < 8; ks++) { load_a(&mapA, ks); load_b(0, ks); }
      for (int t = 1; t < NT; t++) {
        pf_b(t + 2);
        if (MODE == 0 && t == nkv) {
          int i = 0;
          while (ld_acquire(&g_ln_cnt[mtile]) < 128u) { if (++i > (1 << 22)) __trap(); }
          fence_proxy_async_all();
          for (int kc = 0; kc < 8; kc++) load_a(&mapA2, kc);
        }
        for (int ks = 0; ks < 8; ks++) load_b(t, ks);
      }
    } else if (MODE == 0 && tid >= 32) {
      if (tid == 32) { prefetch_map(&mapA2); prefetch_map(&mapB1); prefetch_map(&mapB2); }
      const int lane = tid & 31;
      int n = 0;
      const uint4* p = reinterpret_cast<const uint4*>(x + (size_t)(mtile * 128 + grp * 16 + (tid >> 5) - 1) * DM) + lane;
      uint4 u0 = __ldg(p), u1 = __ldg(p + 32);
      #pragma unroll 1
      for (int i = (tid >> 5) - 1; i < 16; i += 3) {
        const int row = mtile * 128 + grp * 16 + i;
        float a[8], b[8];
        unpack8(u0, a); unpack8(u1, b);
        uint4* qo = reinterpret_cast<uint4*>(out + (size_t)row * DM);
        qo[lane] = u0; qo[32 + lane] = u1;
        p += 3 * DM / 8;
        if (i + 3 < 16) { u0 = __ldg(p); u1 = __ldg(p + 32); }
        ln_row(a, b);
        uint4* q = reinterpret_cast<uint4*>(g_xn + (size_t)row * DM);
        q[lane] = pack8(a); q[32 + lane] = pack8(b);
        n++;
      }
      fence_proxy_async_all();
      __syncwarp();
      if (lane == 0) { __threadfence(); atomicAdd(&g_ln_cnt[mtile], (unsigned)n); }
      if (tid < 64 && blockIdx.x < 2 * FF / 32) {
        const int u = blockIdx.x;
        const bf16* w = (u < FF / 32 ? wgate + u * 32 : wup + (u - FF / 32) * 32) + (size_t)(lane >> 2) * FF + (lane & 3) * 8;
        float s[8] = {0, 0, 0, 0, 0, 0, 0, 0};
        #pragma unroll 1
        for (int i = 0; i < DM / 8; i += 4) {
          uint4 v[4];
          #pragma unroll
          for (int j = 0; j < 4; j++) v[j] = __ldg(reinterpret_cast<const uint4*>(w + (size_t)(i + j) * 8 * FF));
          #pragma unroll
          for (int j = 0; j < 4; j++) {
            float t[8];
            unpack8(v[j], t);
            #pragma unroll
            for (int k = 0; k < 8; k++) s[k] += t[k];
          }
        }
        #pragma unroll
        for (int k = 0; k < 8; k++) {
          s[k] += __shfl_xor_sync(0xffffffffu, s[k], 4); s[k] += __shfl_xor_sync(0xffffffffu, s[k], 8); s[k] += __shfl_xor_sync(0xffffffffu, s[k], 16);
        }
        if (lane < 4) {
          float4* q = reinterpret_cast<float4*>(g_cs + u * 32 + lane * 8);
          q[0] = make_float4(s[0], s[1], s[2], s[3]); q[1] = make_float4(s[4], s[5], s[6], s[7]);
        }
      }
    }
  } else {
    reg_alloc<232>();
    const int wg = wgi - 1, tid_wg = tid & 127;
    const int lane = tid & 31, warp = __shfl_sync(0xffffffffu, tid_wg >> 5, 0);
    const int frow = (lane & 7) + ((lane >> 3) & 1) * 8;
    const RsCtx c{sb, (uint32_t)((wg * 64 + warp * 16 + frow) * 128), (uint32_t)(frow & 7), (uint32_t)(lane >> 4), wg, tid_wg, MODE * 2};
    const uint32_t stage = sb + R_ST + (wg * 4 + warp) * 4096;
    float acc[64];
    uint32_t a[128];
    Ring r{0, 0};
    auto oc0 = [&](int t) { return MODE == 0 ? 0 : t * 128; };
    auto oc1 = [&](int t) { return (MODE == 0 ? slot_of(t) : grp) * S_LEN + mtile * 128 + wg * 64 + warp * 16; };
    rs_tile<true>(acc, a, c, r, wg == 1, true);
    if (MODE == 1 && lane == 0) pdl_wait();
    store_tile(acc, stage, lane, &mapO, oc0(0), oc1(0));
    #pragma unroll 1
    for (int t = 1; t < NT; t++) {
      if (MODE == 0 && t == nkv) rs_swap_a(a, c, r);
      rs_tile<false>(acc, a, c, r, true, wg == 0 || t < NT - 1);
      store_tile(acc, stage, lane, &mapO, oc0(t), oc1(t));
    }
    if (lane == 0) bulk_wait0();
  }
  cluster_arrive_relaxed(); cluster_wait();
}

constexpr int A_NS = 6;
constexpr int A_KR = 0, A_VR = A_NS * 16384;
constexpr int A_QB = 2 * A_NS * 16384;
constexpr int A_BAR = A_QB + 32768;
constexpr int A_SMEM = A_BAR + 256;
constexpr int A_KFULL = A_BAR, A_VFULL = A_BAR + 96;
constexpr int A_QFULL = A_BAR + 192, A_QEV = A_BAR + 208;
constexpr int A_DRY = A_BAR + 224;
constexpr int A_EMPTY = A_NS * 8;
constexpr int N_CLUSTERS = 66;
constexpr int MAX_ITEMS = 8;
struct WeightPtrs { const bf16 *wo, *wg, *wu, *wd, *out; };
struct AttnSched { uint8_t n[N_CLUSTERS]; uint8_t item[N_CLUSTERS][MAX_ITEMS]; };

__device__ __forceinline__ int attn_rowgrp(int rank, bool is_long) {
  return rank == 0 ? (is_long ? 3 : 0) : (is_long ? 2 : 1);
}

constexpr float SM_SC = 0.08838834764831845f * 1.4426950408889634f;
constexpr float SM_LIMIT = 16777216.f;
#define LEAD 2
#define DRYE 1
#define DRYL 0
#define DRY0 1
#define XP 0

template <int J0, int J1>
__device__ __forceinline__ void exp_pack(const float (&s)[32], uint32_t (&p)[16], float m0, float m1, float (&t)[4]) {
  #pragma unroll
  for (int j = J0; j < J1; j++) {
    const float e0 = ex2(fmaf(s[4 * j + 0], SM_SC, -m0)), e1 = ex2(fmaf(s[4 * j + 1], SM_SC, -m0));
    const float e2 = ex2(fmaf(s[4 * j + 2], SM_SC, -m1)), e3 = ex2(fmaf(s[4 * j + 3], SM_SC, -m1));
    if (j == 0) { t[0] = e0; t[1] = e2; t[2] = e1; t[3] = e3; }
    else { t[0] += e0; t[1] += e2; t[2] += e1; t[3] += e3; }
    p[2 * j] = pack_bf16(e0, e1); p[2 * j + 1] = pack_bf16(e2, e3);
  }
}
__device__ __forceinline__ void tile_max(const float (&s)[32], float& x0, float& x1) {
  x0 = fmaxf(s[0], s[1]); x1 = fmaxf(s[2], s[3]);
  #pragma unroll
  for (int j = 1; j < 8; j++) {
    x0 = fmaxf(x0, fmaxf(s[4 * j + 0], s[4 * j + 1]));
    x1 = fmaxf(x1, fmaxf(s[4 * j + 2], s[4 * j + 3]));
  }
  x0 = fmaxf(x0, __shfl_xor_sync(0xffffffffu, x0, 1)); x1 = fmaxf(x1, __shfl_xor_sync(0xffffffffu, x1, 1));
  x0 = fmaxf(x0, __shfl_xor_sync(0xffffffffu, x0, 2)); x1 = fmaxf(x1, __shfl_xor_sync(0xffffffffu, x1, 2));
  x0 *= SM_SC; x1 *= SM_SC;
}
__device__ __forceinline__ void causal_mask(float (&s)[32], int lim) {
  #pragma unroll
  for (int j = 0; j < 8; j++) {
    if (8 * j + 0 > lim) s[4 * j + 0] = -INFINITY;
    if (8 * j + 1 > lim) s[4 * j + 1] = -INFINITY;
    if (8 * j + 0 > lim + 8) s[4 * j + 2] = -INFINITY;
    if (8 * j + 1 > lim + 8) s[4 * j + 3] = -INFINITY;
  }
}
__device__ __forceinline__ void keep_regs(const uint32_t (&a)[16]) {
  #pragma unroll
  for (int i = 0; i < 16; i += 4) asm volatile("" :: "r"(a[i]), "r"(a[i + 1]), "r"(a[i + 2]), "r"(a[i + 3]) : "memory");
}

__device__ __forceinline__ void ring_next(Ring& r) { if (++r.slot == A_NS) { r.slot = 0; r.phase ^= 1; } }

__global__ void __launch_bounds__(384, 1)
attn_kernel(const __grid_constant__ CUtensorMap mapKV, const __grid_constant__ CUtensorMap mapCtx,
            const __grid_constant__ AttnSched sched, const WeightPtrs later) {
  extern __shared__ __align__(1024) uint8_t smem[];
  const uint32_t sb = smem_u32(smem);
  const int tid = threadIdx.x;
  const int wgi = __shfl_sync(0xffffffffu, tid >> 7, 0);
  const uint32_t rank = cluster_ctarank();
  const int cl = blockIdx.x >> 1;
  pdl_launch();
  if (tid == 0) {
    for (int i = 0; i < A_NS; i++) {
      mbar_init(sb + A_KFULL + i * 8, 1); mbar_init(sb + A_KFULL + A_EMPTY + i * 8, 4);
      mbar_init(sb + A_VFULL + i * 8, 1); mbar_init(sb + A_VFULL + A_EMPTY + i * 8, 4);
    }
    for (int i = 0; i < 2; i++) { mbar_init(sb + A_QFULL + i * 8, 1); mbar_init(sb + A_QEV + i * 8, 4); }
    mbar_init(sb + A_DRY, 16);
    asm volatile("fence.mbarrier_init.release.cluster;" ::: "memory");
  }
  __syncthreads();
  cluster_arrive(); cluster_wait();
  const int nitems = sched.n[cl];
  auto rowgrp = [&](int wg, int it) { return attn_rowgrp(rank, ((wg ^ it) & 1) != 0); };
  auto item_row = [&](int wg, int it) { return (sched.item[cl][it] & 7) * 256 + rowgrp(wg, it) * 64; };

  if (wgi == 0) {
    reg_dealloc<24>();
    const int pw = tid >> 5;
    if ((tid & 31) == 0) {
      prefetch_map(&mapKV);
      if (pw >= 2) prefetch_map(&mapCtx);
      pdl_wait();
      if (pw < 2) {
        if (tid == 0) {
          if (blockIdx.x == 0) for (int i = 0; i < 16; i++) g_ln_cnt[i] = 0;
        }
        const uint32_t ring = sb + pw * A_VR + rank * 8192, full = sb + (pw ? A_VFULL : A_KFULL);
        Ring r{0, 1};
        int lead = LEAD - pw;
        int dryw = pw ? A_NS - 2 : -1;
        for (int it = 0; it < nitems; it++) {
          const int item = sched.item[cl][it];
          const int row0 = (pw * NH + (item >> 3)) * S_LEN, m = 4 * (item & 7) + 4;
          if (it == nitems - 1 && blockIdx.x < 128) {
            constexpr int WO_B = HDM * DM * 2 / 128, WF_B = DM * FF * 2 / 128;
            if (pw == 0) { l2_prefetch((const char*)later.wo + blockIdx.x * WO_B, WO_B / 2); l2_prefetch((const char*)later.wo + blockIdx.x * WO_B + WO_B / 2, WO_B / 2); }
            else { l2_prefetch((const char*)later.wg + blockIdx.x * WF_B, WF_B); l2_prefetch((const char*)later.wu + blockIdx.x * WF_B, WF_B);
                   l2_prefetch((const char*)later.wd + blockIdx.x * WF_B, WF_B);
                   l2_prefetch((const char*)later.out + blockIdx.x * (S_LEN * DM * 2 / 128), S_LEN * DM * 2 / 128);
                 }
          }
          for (int x = 0; x < m; x++) {
            if (lead-- == 0) mbar_wait(sb + A_KFULL, 0);
            if (dryw-- == 0) mbar_wait(sb + A_DRY, 0);
            mbar_wait(full + A_EMPTY + r.slot * 8, r.phase);
            mbar_expect_tx(full + r.slot * 8, 16384);
            tma_load_2d_mc(ring + r.slot * 16384, &mapKV, rank * 64, row0 + x * 64, full + r.slot * 8);
            ring_next(r);
          }
        }
      } else {
        const int wg = pw - 2;
        const uint32_t qb = sb + A_QB + wg * 16384, qfull = sb + A_QFULL + wg * 8, qev = sb + A_QEV + wg * 8;
        auto load_q = [&](int it) {
          const int row = (2 * NH + (sched.item[cl][it] >> 3)) * S_LEN + item_row(wg, it);
          mbar_expect_tx(qfull, 16384);
          tma_load_2d(qb, &mapKV, 0, row, qfull);
          tma_load_2d(qb + 8192, &mapKV, 64, row, qfull);
        };
        load_q(0);
        mbar_wait(qev, 0);
        if (nitems > 1) load_q(1);
        for (int e = 0; e < nitems; e++) {
          mbar_wait(qev, (e + 1) & 1);
          fence_proxy_async();
          const int c0 = (sched.item[cl][e] >> 3) * HD, c1 = item_row(wg, e);
          tma_store_2d(&mapCtx, qb, c0, c1);
          tma_store_2d(&mapCtx, qb + 8192, c0 + 64, c1);
          bulk_commit();
          if (e == nitems - 2)
            for (int j = 0; j < e; j++) {
              const int d0 = (sched.item[cl][j] >> 3) * HD, d1 = item_row(wg, j);
              tma_prefetch_2d(&mapCtx, d0, d1); tma_prefetch_2d(&mapCtx, d0 + 64, d1);
            }
          if (e + 1 < nitems) {
            bulk_wait_read0();
            if (e + 2 < nitems) load_q(e + 2); else mbar_arrive(qfull);
          }
        }
        bulk_wait0();
      }
    }
  } else {
    reg_alloc<240>();
    const int wg = wgi - 1, tid_wg = tid & 127;
    const int lane = tid & 31, warp = __shfl_sync(0xffffffffu, tid_wg >> 5, 0);
    const uint32_t qfull = sb + A_QFULL + wg * 8, qev = sb + A_QEV + wg * 8;
    const int frow = (lane & 7) + ((lane >> 3) & 1) * 8;
    const uint32_t fofs = (warp * 16 + frow) * 128;
    uint32_t fbase = sb + A_VR + (A_NS - 2 + wg) * 16384 + fofs;
    const uint32_t fx = (uint32_t)(frow & 7), fhi = (uint32_t)(lane >> 4);
    bool dry = true;
    bool releaser = false;

    float o[64], sA[32], sB[32];
    uint32_t qf[32], pA[16], pB[16];
    float m0 = 1e30f, m1 = 1e30f, l0 = 0.f, l1 = 0.f;
    Ring kr{0, 0}, vr{0, 0};
    uint32_t qpar = 0;

    auto q_fetch = [&]() {
      if (!dry) { mbar_wait(qfull, qpar); qpar ^= 1; }
      #pragma unroll
      for (int k = 0; k < 8; k++)
        ldmatrix_x4(fbase + (k >> 2) * 8192 + ((((k & 3) * 2 + fhi) ^ fx) << 4), qf[4 * k], qf[4 * k + 1], qf[4 * k + 2], qf[4 * k + 3]);
    };
    auto release = [&](uint32_t full, uint32_t slot) { if (releaser) mbar_arrive_cluster(full + A_EMPTY + slot * 8, warp); };
    auto skip = [&](uint32_t full, Ring& r, int cnt) {
      Ring r1 = r; ring_next(r1);
      Ring r2 = r1; ring_next(r2);
      const bool t0 = mbar_test(full + r.slot * 8, r.phase), t1 = mbar_test(full + r1.slot * 8, r1.phase), t2 = mbar_test(full + r2.slot * 8, r2.phase);
      const bool ready = dry || ((t0 || cnt < 1) && (t1 || cnt < 2) && (t2 || cnt < 3));
      #pragma unroll 1
      for (int i = 0; i < cnt; i++) {
        if (!ready) mbar_wait(full + r.slot * 8, r.phase);
        release(full, r.slot);
        ring_next(r);
      }
    };
    auto row_inv = [&](float& s0, float& s1) {
      s0 += __shfl_xor_sync(0xffffffffu, s0, 1); s1 += __shfl_xor_sync(0xffffffffu, s1, 1);
      s0 += __shfl_xor_sync(0xffffffffu, s0, 2); s1 += __shfl_xor_sync(0xffffffffu, s1, 2);
      s0 = 1.0f / s0; s1 = 1.0f / s1;
    };
    auto epilogue = [&](float i0, float i1) {
      #pragma unroll
      for (int q = 0; q < 8; q++) {
        const int jj = 2 * q;
        stmatrix_x4(fbase + (q >> 2) * 8192 + ((((q & 3) * 2 + fhi) ^ fx) << 4),
                    pack_bf16(o[4 * jj + 0] * i0, o[4 * jj + 1] * i0), pack_bf16(o[4 * jj + 2] * i1, o[4 * jj + 3] * i1),
                    pack_bf16(o[4 * jj + 4] * i0, o[4 * jj + 5] * i0), pack_bf16(o[4 * jj + 6] * i1, o[4 * jj + 7] * i1));
      }
      __syncwarp();
      if (lane == 0 && !dry) mbar_arrive(qev);
    };
    uint32_t kprev = 0;
    bool krel = false, ok = false;
    auto issue_qk = [&](float (&s)[32]) {
      const uint64_t dK = make_desc(sb + A_KR + kr.slot * 16384, 16, 1024);
      wgmma_fence();
      #pragma unroll
      for (int k = 0; k < 8; k++) {
        wgmma_rs_n64(s, qf[4 * k], qf[4 * k + 1], qf[4 * k + 2], qf[4 * k + 3], dK + (k >> 2) * 512 + (k & 3) * 2, k != 0);
        if (k == 0 && krel) release(sb + A_KFULL, kprev);
        if (k == 1) {
          Ring kn = kr, vn = vr; ring_next(kn); ring_next(vn);
          const bool a = mbar_test(sb + A_KFULL + kn.slot * 8, kn.phase), b = mbar_test(sb + A_VFULL + vn.slot * 8, vn.phase);
          ok = a && b;
        }
      }
      wgmma_commit();
      kprev = kr.slot; krel = true;
      ring_next(kr);
    };

    int it = 0, i = 0;
    int L = 1;
    int nskip = 1, vskip = 0;
    float e0 = 0.f, e1 = 0.f;
    bool started = true, more = false;
    int nit = 0;
    uint32_t vprev = 0;
    const int lim = warp * 16 + (lane >> 2) - 2 * (lane & 3);

    auto step = [&](float (&cur)[32], float (&nxt)[32], uint32_t (&p)[16], uint32_t (&pprev)[16]) {
      const bool last = i == L - 1;
      if (__builtin_expect(last || i == 0, 0)) {
        if (last && (!dry || warp == DRYL)) {
          causal_mask(cur, lim);
          skip(sb + A_KFULL, kr, nskip);
          more = it + 1 < nit;
          if (more || dry) q_fetch();
        }
        if (i == 0 && (!dry || warp == DRY0)) {
          tile_max(cur, m0, m1);
          e0 = l0; e1 = l1; l0 = 0.f; l1 = 0.f;
          skip(sb + A_VFULL, vr, vskip);
          if (started) row_inv(e0, e1);
        }
        ok = dry;
      }
      float t[4];
      exp_pack<0, XP>(cur, p, m0, m1, t);
      if (__builtin_expect(!ok, 0)) {
        if (more) mbar_wait(sb + A_KFULL + kr.slot * 8, kr.phase);
        mbar_wait(sb + A_VFULL + vr.slot * 8, vr.phase);
      }
      issue_qk(nxt);
      exp_pack<XP, 8>(cur, p, m0, m1, t);
      float r0 = t[0] + t[2], r1 = t[1] + t[3];
      if (__builtin_expect(__any_sync(0xffffffffu, !(fmaxf(r0, r1) <= SM_LIMIT)), 0)) {
        wgmma_wait<0>();
        fence_regs(o);
        float x0, x1;
        tile_max(cur, x0, x1);
        x0 = fmaxf(x0, m0); x1 = fmaxf(x1, m1);
        const float a0 = i == 0 ? 1.f : ex2(m0 - x0), a1 = i == 0 ? 1.f : ex2(m1 - x1);
        l0 *= a0; l1 *= a1; m0 = x0; m1 = x1;
        #pragma unroll
        for (int j = 0; j < 16; j++) { o[4 * j] *= a0; o[4 * j + 1] *= a0; o[4 * j + 2] *= a1; o[4 * j + 3] *= a1; }
        exp_pack<0, 8>(cur, p, x0, x1, t);
        r0 = t[0] + t[2]; r1 = t[1] + t[3];
      }
      l0 += r0; l1 += r1;
      const uint64_t dV = make_desc(sb + A_VR + vr.slot * 16384, 8192, 1024);
      wgmma_wait<1>();
      fence_regs(o);
      keep_regs(pprev);
      if (__builtin_expect(i == 0 && started && (!dry || warp == DRYE), 0)) epilogue(e0, e1);
      const int acc = i != 0;
      wgmma_fence();
      #pragma unroll
      for (int k = 0; k < 4; k++) {
        wgmma_rs_n128_tb(o, p[4 * k], p[4 * k + 1], p[4 * k + 2], p[4 * k + 3], dV + k * 128, acc || k != 0);
        if (k == 0 && started) release(sb + A_VFULL, vprev);
      }
      wgmma_commit();
      started = true;
      vprev = vr.slot;
      ring_next(vr);
      wgmma_wait<1>();
      fence_regs(nxt);
      if (__builtin_expect(last, 0)) {
        vskip = nskip; i = 0;
        if (more) { ++it; L = 4 * (sched.item[cl][it] & 7) + rowgrp(wg, it) + 1; nskip = 3 - rowgrp(wg, it); }
      } else ++i;
    };
    #pragma unroll 1
    while (true) {
      if (!dry) pdl_wait();
      q_fetch();
      __syncwarp();
      if (lane == 0 && !dry) mbar_arrive(qev);
      if (!dry) mbar_wait(sb + A_KFULL, 0);
      issue_qk(sA);
      wgmma_wait<0>();
      fence_regs(sA);
      ok = false;
      #pragma unroll 1
      do {
        if (!dry || wg == 0) step(sA, sB, pA, pB); else wgmma_wait<0>();
        if (!dry || wg == 1) step(sB, sA, pB, pA); else wgmma_wait<0>();
      } while (more);
      if (!dry) break;
      wgmma_wait<0>();
      fence_regs(o);
      keep_regs(pB);
      fence_proxy_async();
      __syncwarp();
      if (lane < 2) mbar_arrive_cluster(sb + A_DRY, lane);
      dry = false;
      releaser = lane == 0 && warp < 2;
      fbase = sb + A_QB + wg * 16384 + fofs;
      kr = Ring{0, 0}; vr = Ring{0, 0};
      krel = false; started = false; more = true; nit = nitems;
      l0 = 0.f; l1 = 0.f;
      it = 0; i = 0; vskip = 0;
      L = 4 * (sched.item[cl][0] & 7) + rowgrp(wg, 0) + 1;
      nskip = 3 - rowgrp(wg, 0);
    }
    row_inv(l0, l1);
    wgmma_wait<0>();
    fence_regs(o);
    keep_regs(pB);
    release(sb + A_VFULL, vprev);
    skip(sb + A_VFULL, vr, vskip);
    if (nitems > 1) mbar_wait(qfull, qpar);
    epilogue(l0, l1);
  }
  cluster_arrive(); cluster_wait();
}

#define T_DRYH 1
#define T_DH 1
#define T_DD 0
#define T_DRYG 1
#define DSTAG 1
constexpr int FS = FF / NSPLIT;
constexpr int T_NS = 11;
constexpr int T_ST = T_NS * 16384;
constexpr int T_BAR = T_ST + 2 * 24576;
constexpr int T_FULL = T_BAR, T_EMPTY = T_BAR + 128;
constexpr int T_SFULL = T_BAR + 88, T_SEMPTY = T_BAR + 104, T_CSF = T_BAR + 120;
constexpr int T_RDY = T_BAR + 216;
constexpr int T_CS = T_BAR + 272;
constexpr int T_SMEM = T_CS + 2 * FS * 4;
static_assert(T_SMEM <= 232448, "smem");

__device__ __forceinline__ void tnext(Ring& r) { if (++r.slot == T_NS) { r.slot = 0; r.phase ^= 1; } }
__device__ __forceinline__ Ring tadv(Ring r, int n) { for (int i = 0; i < n; i++) tnext(r); return r; }
__device__ __forceinline__ void tma_red_2d(const CUtensorMap* map, uint32_t src, int c0, int c1) {
  asm volatile("cp.reduce.async.bulk.tensor.2d.global.shared::cta.add.tile.bulk_group [%0, {%2, %3}], [%1];"
               :: "l"(map), "r"(src), "r"(c0), "r"(c1) : "memory");
}
__device__ __forceinline__ void red_release(unsigned* p, unsigned v) {
  asm volatile("red.release.gpu.global.add.u32 [%0], %1;" :: "l"(p), "r"(v) : "memory");
}
__device__ __forceinline__ void red_relaxed(unsigned* p, unsigned v) {
  asm volatile("red.relaxed.gpu.global.add.u32 [%0], %1;" :: "l"(p), "r"(v) : "memory");
}
__device__ __forceinline__ void sts128(uint32_t addr, uint32_t x, uint32_t y, uint32_t z, uint32_t w) {
  asm volatile("st.shared.v4.b32 [%0], {%1, %2, %3, %4};" :: "r"(addr), "r"(x), "r"(y), "r"(z), "r"(w) : "memory");
}
__device__ __forceinline__ void lds128(uint32_t addr, uint32_t& x, uint32_t& y, uint32_t& z, uint32_t& w) {
  asm volatile("ld.shared.v4.b32 {%0, %1, %2, %3}, [%4];" : "=r"(x), "=r"(y), "=r"(z), "=r"(w) : "r"(addr) : "memory");
}

struct RowStat { float s0, q0, s1, q1; };
__device__ __forceinline__ void stat_smem(float& s, float& q, uint32_t base, int lane) {
  const uint32_t p = base + (lane >> 1) * 128 + (lane & 1) * 64;
  float s1 = 0.f, q1 = 0.f;
  #pragma unroll
  for (int j = 0; j < 4; j++) {
    uint32_t v[4];
    lds128(p + (((j + (lane >> 1)) & 3) << 4), v[0], v[1], v[2], v[3]);
    #pragma unroll
    for (int i = 0; i < 4; i++) {
      const float x0 = __uint_as_float(v[i] << 16), x1 = __uint_as_float(v[i] & 0xffff0000u);
      s += x0; q = fmaf(x0, x0, q); s1 += x1; q1 = fmaf(x1, x1, q1);
    }
  }
  s += s1; q += q1;
}
__device__ __forceinline__ RowStat stat_finish(float s, float q, int lane) {
  s += __shfl_xor_sync(0xffffffffu, s, 1); q += __shfl_xor_sync(0xffffffffu, q, 1);
  const float m = s * (1.0f / DM);
  const float sd = sqrtf(fmaxf(q * (1.0f / DM) - m * m, 0.f) + LN_EPS);
  const int src = (lane >> 2) * 2;
  RowStat st;
  st.s0 = -__shfl_sync(0xffffffffu, m, src); st.s1 = -__shfl_sync(0xffffffffu, m, src + 16);
  st.q0 = __shfl_sync(0xffffffffu, sd, src); st.q1 = __shfl_sync(0xffffffffu, sd, src + 16);
  return st;
}
__device__ __forceinline__ float glu_ln(float ag, float au, float cg, float cu, float nm, float kl, float sd) {
  const float e = ex2(fmaf(nm, cg, ag) * kl);
  float r;
  asm("rcp.approx.ftz.f32 %0, %1;" : "=f"(r) : "f"(fmaf(e, sd, sd)));
  return fmaf(nm, cu, au) * r;
}
template <int NJ, typename F>
__device__ __forceinline__ void glu_tile(const float (&acc)[64], const RowStat& st, uint32_t cs, F sink) {
  const float k0 = __fdividef(-1.4426950408889634f, st.q0), k1 = __fdividef(-1.4426950408889634f, st.q1);
  #pragma unroll
  for (int q = 0; q < NJ / 2; q++) {
    uint32_t v[4];
    #pragma unroll
    for (int i = 0; i < 2; i++) {
      const int j = 2 * q + i;
      float cg0, cg1, cu0, cu1;
      asm volatile("ld.shared.v2.f32 {%0, %1}, [%2];" : "=f"(cg0), "=f"(cg1) : "r"(cs + j * 32));
      asm volatile("ld.shared.v2.f32 {%0, %1}, [%2];" : "=f"(cu0), "=f"(cu1) : "r"(cs + FS * 4 + j * 32));
      const float* g = &acc[4 * j];
      const float* u = &acc[32 + 4 * j];
      v[2 * i]     = pack_bf16(glu_ln(g[0], u[0], cg0, cu0, st.s0, k0, st.q0), glu_ln(g[1], u[1], cg1, cu1, st.s0, k0, st.q0));
      v[2 * i + 1] = pack_bf16(glu_ln(g[2], u[2], cg0, cu0, st.s1, k1, st.q1), glu_ln(g[3], u[3], cg1, cu1, st.s1, k1, st.q1));
    }
    sink(q, v[0], v[1], v[2], v[3]);
  }
}

struct TCtx { uint32_t sb, arow, fx, fhi, stage; int wg, tid_wg, lane, warp; };
__device__ __forceinline__ void t_rel(const TCtx& c, uint32_t slot) { release_slot(c.sb + T_EMPTY + slot * 8, c.tid_wg); }
__device__ __forceinline__ void t_wait(const TCtx& c, const Ring& r) { mbar_wait(c.sb + T_FULL + r.slot * 8, r.phase); }

enum { K_FIRST = 0, K_FULL = 1, K_SUB = 2, K_HALF = 3, K_DOWN = 4 };
template <int KIND>
__device__ __forceinline__ void t_tile(float (&acc)[64], uint32_t (&a)[128], const TCtx& c, Ring& r, bool tok_wait, bool tok_pass, bool s0 = false, bool dry = false) {
  constexpr bool FIRST = KIND == K_FIRST;
  constexpr int NK = KIND == K_DOWN ? 4 : 8;
  uint32_t b1 = 0, b2 = 0, a1 = 0, a2 = 0, curA = 0;
  bool ok = false;
  #pragma unroll
  for (int ks = 0; ks < NK; ks++) {
    if (FIRST) {
      t_wait(c, r);
      fetch_a(a, ks, c.sb + r.slot * 16384 + c.arow, c.fx, c.fhi);
      curA = r.slot; tnext(r);
    }
    if (KIND == K_SUB && ks == 6 && s0) {
      const Ring x = c.wg ? tadv(r, 3) : r;
      const uint32_t src = c.sb + x.slot * 16384 + (c.arow & 8191);
      if (c.wg) { t_wait(c, r); t_rel(c, r.slot); }
      t_wait(c, x);
      fetch_a(a, 6, src, c.fx, c.fhi);
      fetch_a(a, 7, src + 8192, c.fx, c.fhi);
      tnext(r);
      ok = false;
    }
    if (!ok && !dry) t_wait(c, r);
    if (ks == (FIRST ? WAIT0 : 0) && tok_wait) bar_sync(1 + c.wg, 256);
    const uint64_t dB = make_desc(c.sb + r.slot * 16384, 8192, 1024);
    const uint32_t b0 = r.slot;
    tnext(r);
    wgmma_fence();
    #pragma unroll
    for (int k = 0; k < (KIND == K_DOWN && ks == 3 ? 2 : 4); k++) {
      const uint32_t* f = &a[16 * ks + 4 * k];
      if (KIND == K_HALF) {
        wgmma_rs_n32_tb<0>(acc, f[0], f[1], f[2], f[3], dB + k * 128, (ks | k) != 0);
        wgmma_rs_n32_tb<32>(acc, f[0], f[1], f[2], f[3], dB + 512 + k * 128, (ks | k) != 0);
      } else {
        wgmma_rs_n128_tb(acc, f[0], f[1], f[2], f[3], dB + k * 128, (ks | k) != 0);
      }
      if (k == 0 && ks >= 2) {
        wgmma_wait<1>();
        if (!dry) t_rel(c, b2);
        if (FIRST) t_rel(c, a2);
      }
      if (k == 1 && !FIRST && ks < NK - 1) ok = mbar_test(c.sb + T_FULL + r.slot * 8, r.phase);
    }
    wgmma_commit();
    if (ks == NK - 1 && tok_pass) bar_arrive(2 - c.wg, 256);
    b2 = b1; b1 = b0; a2 = a1; a1 = curA;
  }
  wgmma_wait<1>();
  if (!dry) t_rel(c, b2);
  if (FIRST) t_rel(c, a2);
  wgmma_wait<0>();
  fence_regs(acc);
  if (!dry) t_rel(c, b1);
  if (FIRST) t_rel(c, a1);
}
__device__ __forceinline__ void t_store(const float (&acc)[64], const TCtx& c, uint32_t& spar, bool dry = false) {
  mbar_wait(c.sb + T_SEMPTY + c.wg * 8, spar ^ 1);
  const int row = (c.lane & 7) + ((c.lane >> 3) & 1) * 8;
  const uint32_t rbase = c.stage + row * 128;
  #pragma unroll
  for (int q = 0; q < 8; q++) {
    const int j = 2 * q;
    const int chunk = 2 * (q & 3) + (c.lane >> 4);
    stmatrix_x4(rbase + (q >> 2) * 8192 + ((chunk ^ (row & 7)) << 4),
                pack_bf16(acc[4 * j + 0], acc[4 * j + 1]), pack_bf16(acc[4 * j + 2], acc[4 * j + 3]),
                pack_bf16(acc[4 * j + 4], acc[4 * j + 5]), pack_bf16(acc[4 * j + 6], acc[4 * j + 7]));
  }
  fence_proxy_async();
  __syncwarp();
  if (c.lane == 0 && !dry) mbar_arrive(c.sb + T_SFULL + c.wg * 8);
  if (!dry) spar ^= 1;
}
__device__ __forceinline__ void zero_acc(float (&acc)[64]) {
  #pragma unroll
  for (int i = 0; i < 64; i++) acc[i] = 0.f;
}
__global__ void __launch_bounds__(384, 1)
tail_kernel(const __grid_constant__ CUtensorMap mapCtx, const __grid_constant__ CUtensorMap mapWo,
            const __grid_constant__ CUtensorMap mapH128, const __grid_constant__ CUtensorMap mapH64,
            const __grid_constant__ CUtensorMap mapWg, const __grid_constant__ CUtensorMap mapWu,
            const __grid_constant__ CUtensorMap mapWd) {
  extern __shared__ __align__(1024) uint8_t smem[];
  const uint32_t sb = smem_u32(smem);
  const int tid = threadIdx.x;
  const int wgi = __shfl_sync(0xffffffffu, tid >> 7, 0);
  const uint32_t rank = cluster_ctarank();
  const int cl = blockIdx.x >> 1;
  const int mtile = (cl & 7) * 2 + rank;
  const int grp = cl >> 3;
  const int ak0 = grp * 512, f0 = grp * FS;
  unsigned* const cnt = g_tail_cnt + mtile * 32;
  auto put_b = [&](int slot, const CUtensorMap* m, int c0, int c1) {
    mbar_expect_tx(sb + T_FULL + slot * 8, 16384);
    tma_load_2d_mc(sb + slot * 16384 + rank * 8192, m, c0, c1, sb + T_FULL + slot * 8);
  };
  auto put_a = [&](int slot, const CUtensorMap* m, int c0) {
    mbar_expect_tx(sb + T_FULL + slot * 8, 16384);
    tma_load_2d(sb + slot * 16384, m, c0, mtile * 128, sb + T_FULL + slot * 8);
  };
  if (tid == 0) {
    prefetch_map(&mapWo); prefetch_map(&mapCtx);
    for (int i = 0; i < T_NS; i++) { mbar_init(sb + T_FULL + i * 8, 1); mbar_init(sb + T_EMPTY + i * 8, 4); }
    for (int i = 0; i < 2; i++) { mbar_init(sb + T_SFULL + i * 8, 4); mbar_init(sb + T_SEMPTY + i * 8, 1); }
    for (int i = 0; i < 6; i++) mbar_init(sb + T_RDY + i * 8, i < 3 ? 2 : 1);
    mbar_init(sb + T_CSF, 1);
    asm volatile("fence.mbarrier_init.release.cluster;" ::: "memory");
    fence_proxy_async();
  }
  __syncthreads();
  cluster_arrive_relaxed(); cluster_wait();
  if (tid == 0)
    for (int ks = 0; ks < T_NS / 2; ks++) put_b(2 * ks + 1, &mapWo, rank * 64, ak0 + ks * 64);

  if (wgi == 0) {
    reg_dealloc<40>();
    const int pw = tid >> 5;
    if (tid == 0) {
      Ring r{0, 1};
      auto load_b = [&](const CUtensorMap* m, int c0, int c1) { mbar_wait(sb + T_EMPTY + r.slot * 8, r.phase); put_b(r.slot, m, c0, c1); tnext(r); };
      auto load_a = [&](const CUtensorMap* m, int c0) { mbar_wait(sb + T_EMPTY + r.slot * 8, r.phase); put_a(r.slot, m, c0); tnext(r); };
      auto load_q = [&](int half) {
        mbar_wait(sb + T_EMPTY + r.slot * 8, r.phase);
        mbar_wait(sb + T_RDY + (3 + half) * 8, 0);
        mbar_expect_tx(sb + T_FULL + r.slot * 8, 16384);
        tma_load_2d(sb + r.slot * 16384, &mapH64, 384, mtile * 128 + half * 64, sb + T_FULL + r.slot * 8);
        tma_load_2d(sb + r.slot * 16384 + 8192, &mapH64, 448, mtile * 128 + half * 64, sb + T_FULL + r.slot * 8);
        tnext(r);
      };
      pdl_wait();
      for (int ks = 0; ks <= T_NS / 2; ks++) put_a(2 * ks, &mapCtx, ak0 + ks * 64);
      mbar_expect_tx(sb + T_CSF, 2 * FS * 4);
      asm volatile("cp.async.bulk.shared::cluster.global.mbarrier::complete_tx::bytes [%0], [%1], %2, [%3];"
                   :: "r"(sb + T_CS), "l"(g_cs + f0), "r"(FS * 4), "r"(sb + T_CSF) : "memory");
      asm volatile("cp.async.bulk.shared::cluster.global.mbarrier::complete_tx::bytes [%0], [%1], %2, [%3];"
                   :: "r"(sb + T_CS + FS * 4), "l"(g_cs + FF + f0), "r"(FS * 4), "r"(sb + T_CSF) : "memory");
      prefetch_map(&mapH128); prefetch_map(&mapH64); prefetch_map(&mapWg); prefetch_map(&mapWu); prefetch_map(&mapWd);
      r = tadv(r, T_NS);
      for (int e = T_NS; e < 16; e++) {
        if (e & 1) load_b(&mapWo, rank * 64, ak0 + (e >> 1) * 64); else load_a(&mapCtx, ak0 + (e >> 1) * 64);
      }
      for (int t = 1; t < 4; t++)
        for (int ks = 0; ks < 8; ks++) load_b(&mapWo, t * 128 + rank * 64, ak0 + ks * 64);
      const CUtensorMap* mgu = rank ? &mapWu : &mapWg;
      for (int kc = 0; kc < 6; kc++) {
        mbar_wait(sb + T_EMPTY + r.slot * 8, r.phase);
        if (!(kc & 1)) mbar_wait(sb + T_RDY + (kc >> 1) * 8, 0);
        put_a(r.slot, &mapH128, kc * 64);
        tnext(r);
      }
      for (int ks = 0; ks < 6; ks++) load_b(mgu, f0, ks * 64);
      load_q(0);
      load_b(mgu, f0, 6 * 64); load_b(mgu, f0, 7 * 64);
      load_q(1);
      for (int sub = 1; sub < 4; sub++)
        for (int ks = 0; ks < 8; ks++) load_b(mgu, f0 + sub * 64, ks * 64);
      for (int t = 0; t < 4; t++)
        for (int ks = 0; ks < 4; ks++) load_b(&mapWd, ((t + DSTAG * grp) & 3) * 128 + rank * 64, f0 + ks * 64);
    } else if (tid == 32 || tid == 64) {
      const int wg = pw - 1;
      const uint32_t stage = sb + T_ST + wg * 24576;
      const int row = mtile * 128 + wg * 64;
      pdl_wait();
      #pragma unroll 1
      for (int e = 0; e < 8; e++) {
        mbar_wait(sb + T_SFULL + wg * 8, e & 1);
        {
          const int col = ((e < 4 ? e : e + DSTAG * grp) & 3) * 128;
          tma_red_2d(&mapH64, stage, col, row);
          tma_red_2d(&mapH64, stage + 8192, col + 64, row);
        }
        bulk_commit();
        bulk_wait_read0();
        mbar_arrive(sb + T_SEMPTY + wg * 8);
        if (e < 4) {
          bulk_wait0();
          red_relaxed(cnt + wg * 4 + e, 1);
        }
      }
      bulk_wait0();
    } else if (pw == 3) {
      const int lane = tid & 31;
      pdl_wait();
      bool done = lane > 8;
      const unsigned* pc = cnt + (lane == 8 ? 8 : (lane & 1) * 4 + (lane >> 1));
      const unsigned need = lane == 8 ? 2 * NSPLIT : NSPLIT;
      int it = 0;
      while (!__all_sync(0xffffffffu, done)) {
        if (!done && ld_acquire(pc) >= need) {
          done = true;
          mbar_arrive(sb + T_RDY + (lane < 6 ? lane >> 1 : lane - 3) * 8);
        }
        if (++it > (1 << 22)) __trap();
      }
    }
  } else {
    reg_alloc<232>();
    const int wg = wgi - 1, tid_wg = tid & 127;
    const int lane = tid & 31;
    const TCtx cz{sb, 0, 0, 0, (uint32_t)(sb + T_ST + wg * 24576 + (tid_wg >> 5) * 2048), wg, tid_wg, lane, 0};
    float acc[64];
    uint32_t a[128];
    uint32_t spar = 0;
    Ring r{0, 0};
    bool dry = true;
    const uint32_t cs = sb + T_CS + (lane & 3) * 8;
    const uint32_t spill = cz.stage + lane * 16;
    RowStat st{0.f, 0.f, 0.f, 0.f};
    #pragma unroll 1
    while (true) {
    if (!dry) {
    uint32_t tid2;
    asm volatile("mov.u32 %0, %%tid.x;" : "=r"(tid2));
    const int frow = (tid2 & 7) + ((tid2 >> 3) & 1) * 8;
    const int warp = __shfl_sync(0xffffffffu, (tid2 >> 5) & 3, 0);
    const TCtx c{sb, (uint32_t)((wg * 64 + warp * 16 + frow) * 128), (uint32_t)(frow & 7), (tid2 >> 4) & 1, cz.stage, wg, tid_wg, lane, warp};
    zero_acc(acc);
    t_tile<K_FIRST>(acc, a, c, r, wg == 1, true);
    t_store(acc, c, spar);
    #pragma unroll 1
    for (int t = 1; t < 4; t++) {
      t_tile<K_FULL>(acc, a, c, r, true, true);
      t_store(acc, c, spar);
    }
    float hs = 0.f, hq = 0.f;
    const uint32_t wrow = (uint32_t)(warp * 16 * 128);
    {
      Ring ra = r;
      #pragma unroll
      for (int kc = 0; kc < 3; kc++) { t_wait(c, r); fetch_a(a, kc, sb + r.slot * 16384 + c.arow, c.fx, c.fhi); tnext(r); }
      #pragma unroll 1
      for (int kc = 0; kc < 6; kc++) {
        if (kc >= 3) t_wait(c, ra);
        stat_smem(hs, hq, sb + ra.slot * 16384 + wg * 8192 + wrow, lane);
        if (kc < 3) { bar_sync(3 + wg, 128); t_rel(c, ra.slot); }
        tnext(ra);
      }
      ra = r;
      #pragma unroll
      for (int kc = 3; kc < 6; kc++) { fetch_a(a, kc, sb + r.slot * 16384 + c.arow, c.fx, c.fhi); tnext(r); }
      bar_sync(3 + wg, 128);
      #pragma unroll 1
      for (int kc = 3; kc < 6; kc++) { t_rel(c, ra.slot); tnext(ra); }
    }
    #pragma unroll 1
    for (int s = 0; s < 3; s++) {
      t_tile<K_SUB>(acc, a, c, r, true, true, s == 0);
      const Ring y = r;
      if (s == 0) {
        if (tid_wg == 0) {
          uint32_t bid;
          asm volatile("mov.u32 %0, %%ctaid.x;" : "=r"(bid));
          red_relaxed(g_tail_cnt + (((bid >> 1) & 7) * 2 + (bid & 1)) * 32 + 8, 1);
        }
        const uint32_t own = wg ? r.slot : (r.slot + T_NS - 3) % T_NS;
        #pragma unroll 1
        for (int j = 0; j < 2; j++) stat_smem(hs, hq, sb + own * 16384 + j * 8192 + wrow, lane);
        bar_sync(3 + wg, 128);
        t_rel(c, own);
        st = stat_finish(hs, hq, lane);
        mbar_wait(sb + T_CSF, 0);
        mbar_wait(sb + T_SEMPTY + wg * 8, spar ^ 1);
        tnext(r);
      }
      glu_tile<8>(acc, st, cs + s * 256, [&](int q, uint32_t v0, uint32_t v1, uint32_t v2, uint32_t v3) { sts128(spill + s * 8192 + q * 512, v0, v1, v2, v3); });
      if (s == 0 && wg == 0) { t_wait(c, y); t_rel(c, y.slot); }
    }
    }
    if (!dry || (T_DH && wg == T_DRYH)) {
      zero_acc(acc);
      t_tile<K_HALF>(acc, a, cz, r, !dry, !dry, false, dry);
      if (!dry || T_DRYG) {
      glu_tile<4>(acc, st, cs + 3 * 256, [&](int q, uint32_t v0, uint32_t v1, uint32_t v2, uint32_t v3) {
        a[48 + 4 * q] = v0; a[49 + 4 * q] = v1; a[50 + 4 * q] = v2; a[51 + 4 * q] = v3; });
      #pragma unroll
      for (int j = 0; j < 3; j++)
        #pragma unroll
        for (int q = 0; q < 4; q++) lds128(spill + j * 8192 + q * 512, a[16 * j + 4 * q], a[16 * j + 4 * q + 1], a[16 * j + 4 * q + 2], a[16 * j + 4 * q + 3]);
      if (!dry) mbar_wait(sb + T_RDY + 40, 0);
      }
    }
    if (!dry || (T_DD == 1 && wg != T_DRYH) || (T_DD == 2 && wg == T_DRYH)) {
      zero_acc(acc);
      const int nt = dry ? 1 : 4;
      #pragma unroll 1
      for (int t = 0; t < nt; t++) {
        t_tile<K_DOWN>(acc, a, cz, r, !dry, !dry && (wg == 0 || t < 3), false, dry);
        t_store(acc, cz, spar, dry);
      }
    }
    if (!dry) break;
    dry = false;
    r = Ring{0, 0};
    }
  }
  cluster_arrive_relaxed(); cluster_wait();
}

typedef CUresult (*PFN_encodeTiled)(CUtensorMap*, CUtensorMapDataType, cuuint32_t, void*, const cuuint64_t*, const cuuint64_t*,
                                    const cuuint32_t*, const cuuint32_t*, CUtensorMapInterleave, CUtensorMapSwizzle,
                                    CUtensorMapL2promotion, CUtensorMapFloatOOBfill);

static CUtensorMap make_map(PFN_encodeTiled enc, const void* ptr, uint64_t rows, uint64_t cols, uint32_t box_rows, uint32_t box_cols) {
  CUtensorMap m;
  cuuint64_t dims[2] = {cols, rows};
  cuuint64_t strides[1] = {cols * 2};
  cuuint32_t box[2] = {box_cols, box_rows};
  cuuint32_t es[2] = {1, 1};
  enc(&m, CU_TENSOR_MAP_DATA_TYPE_BFLOAT16, 2, const_cast<void*>(ptr), dims, strides, box, es, CU_TENSOR_MAP_INTERLEAVE_NONE,
      CU_TENSOR_MAP_SWIZZLE_128B, CU_TENSOR_MAP_L2_PROMOTION_L2_128B, CU_TENSOR_MAP_FLOAT_OOB_FILL_NONE);
  return m;
}

static void build_sched(AttnSched& sc) {
  for (int c = 0; c < N_CLUSTERS; c++) { sc.n[c] = 0; for (int i = 0; i < MAX_ITEMS; i++) sc.item[c][i] = 0; }
  for (int c = 0; c < 64; c++) {
    const int p = c & 3, i = c >> 2;
    for (int ph = 0; ph < 2; ph++) {
      const int h = (i >> 2) * 8 + (i & 3) + (ph == 0 ? 4 : 0);
      const int ja = ph == 0 ? p : 7 - p;
      sc.item[c][sc.n[c]++] = (uint8_t)(h * 8 + ja);
      sc.item[c][sc.n[c]++] = (uint8_t)(h * 8 + 7 - ja);
    }
  }
}

template <typename... KArgs, typename... Args>
static void launch(void (*kern)(KArgs...), int grid, int block, int smem, int cluster, bool pdl, Args... args) {
  cudaLaunchConfig_t cfg = {};
  cfg.gridDim = dim3(grid); cfg.blockDim = dim3(block); cfg.dynamicSmemBytes = smem; cfg.stream = cudaStreamPerThread;
  cudaLaunchAttribute at[2];
  int n = 0;
  if (cluster > 1) { at[n].id = cudaLaunchAttributeClusterDimension; at[n].val.clusterDim.x = cluster; at[n].val.clusterDim.y = 1; at[n].val.clusterDim.z = 1; n++; }
  if (pdl) { at[n].id = cudaLaunchAttributeProgrammaticStreamSerialization; at[n].val.programmaticStreamSerializationAllowed = 1; n++; }
  cfg.attrs = at; cfg.numAttrs = n;
  cudaLaunchKernelEx(&cfg, kern, args...);
}


extern "C" void kernel_launch(void* const* d_in, const int* in_sizes, int n_in, void* d_out, int out_size) {
  const bf16* x   = (const bf16*)d_in[0];
  const bf16* ckv = (const bf16*)d_in[1];
  const bf16* wq  = (const bf16*)d_in[2];
  const bf16* wuk = (const bf16*)d_in[3];
  const bf16* wuv = (const bf16*)d_in[4];
  const bf16* wo  = (const bf16*)d_in[5];
  const bf16* wg  = (const bf16*)d_in[7];
  const bf16* wu  = (const bf16*)d_in[8];
  const bf16* wd  = (const bf16*)d_in[9];
  bf16* out = (bf16*)d_out;

  static PFN_encodeTiled enc = nullptr;
  static void *p_xn, *p_kv, *p_ctx;
  static AttnSched sched;
  if (!enc) {
    void* fn = nullptr; cudaDriverEntryPointQueryResult qr;
    cudaGetDriverEntryPoint("cuTensorMapEncodeTiled", &fn, cudaEnableDefault, &qr);
    enc = (PFN_encodeTiled)fn;
    cudaGetSymbolAddress(&p_xn, g_xn); cudaGetSymbolAddress(&p_kv, g_qkv); cudaGetSymbolAddress(&p_ctx, g_ctx);
    cudaFuncSetAttribute(gemm_kernel<0>, cudaFuncAttributeMaxDynamicSharedMemorySize, R_SMEM);
    cudaFuncSetAttribute(attn_kernel, cudaFuncAttributeMaxDynamicSharedMemorySize, A_SMEM);
    cudaFuncSetAttribute(tail_kernel, cudaFuncAttributeMaxDynamicSharedMemorySize, T_SMEM);
    build_sched(sched);
  }
  const CUtensorMap m_c    = make_map(enc, ckv, S_LEN, DM, 128, 64);
  const CUtensorMap m_wuk  = make_map(enc, wuk, DM, HDM, 64, 64);
  const CUtensorMap m_wuv  = make_map(enc, wuv, DM, HDM, 64, 64);
  const CUtensorMap m_kv_s = make_map(enc, p_kv, 3 * NH * S_LEN, HD, 16, 64);
  const CUtensorMap m_kv_l = make_map(enc, p_kv, 3 * NH * S_LEN, HD, 64, 64);
  const CUtensorMap m_xn   = make_map(enc, p_xn, S_LEN, DM, 128, 64);
  const CUtensorMap m_wq   = make_map(enc, wq, DM, HDM, 64, 64);
  const CUtensorMap m_ctx_s = make_map(enc, p_ctx, S_LEN, HDM, 64, 64);
  const CUtensorMap m_ctx_l = make_map(enc, p_ctx, S_LEN, HDM, 128, 64);
  const CUtensorMap m_wo   = make_map(enc, wo, HDM, DM, 64, 64);
  const CUtensorMap m_h128 = make_map(enc, out, S_LEN, DM, 128, 64);
  const CUtensorMap m_h64  = make_map(enc, out, S_LEN, DM, 64, 64);
  const CUtensorMap m_wg   = make_map(enc, wg, DM, FF, 64, 64);
  const CUtensorMap m_wu   = make_map(enc, wu, DM, FF, 64, 64);
  const CUtensorMap m_wd   = make_map(enc, wd, FF, DM, 64, 64);

  launch(gemm_kernel<0>, 128, 384, R_SMEM, 2, false, m_c, m_xn, m_wuk, m_wuv, m_wq, m_kv_s, x, ckv, wuk, wuv, wg, wu, out);
  launch(attn_kernel, 128, 384, A_SMEM, 2, true, m_kv_l, m_ctx_s, sched, WeightPtrs{wo, wg, wu, wd, out});
  launch(tail_kernel, 128, 384, T_SMEM, 2, true, m_ctx_l, m_wo, m_h128, m_h64, m_wg, m_wu, m_wd);
}
```
